```python
import torch

def _softmax(x, axis=-1):
    return torch.softmax(x, dim=axis)
def _gelu(x):
    return torch.nn.functional.gelu(x, approximate="tanh")
def _silu(x):
    return torch.nn.functional.silu(x)
def _sigmoid(x):
    return torch.sigmoid(x)
def _layernorm(x, axis=-1, eps=1e-5):
    m = x.mean(dim=axis, keepdim=True)
    v = x.var(dim=axis, keepdim=True, unbiased=False)
    return (x - m) / torch.sqrt(v + eps)
def _scatter_add(tgt, idx, src, axis=0):
    return tgt.clone().index_add_(axis, idx, src)
def _segment_sum(src, seg, n):
    out = torch.zeros((n,) + src.shape[1:], dtype=src.dtype)
    return out.index_add_(0, seg, src)
def _pad(x, pw):
    flat = tuple(v for pair in reversed(pw) for v in pair)
    return torch.nn.functional.pad(x, flat)

kernel_name = 'parallel_sum__softmax_full_mha__glu_gated_reglu__prompt'

def setup_inputs():

    _w = (lambda a: (lambda t: t.to(torch.bfloat16) if t.is_floating_point() else t)(torch.as_tensor(a)))
    def _A_setup():
        B, S, D = 1, 2048, 512
        return {
            "x": _w((lambda *s: torch.randn(*s, dtype=torch.bfloat16) * 0.05)(B, S, D)),
            "wqkv": _w((lambda *s: torch.randn(*s, dtype=torch.bfloat16) * 0.05)(D, 3 * D)),
            "wo": _w((lambda *s: torch.randn(*s, dtype=torch.bfloat16) * 0.05)(D, D)),
        }
    _A_in = _A_setup()

    def _B_setup():
        B, S, D, F = 1, 2048, 512, 1376
        return {
            "x": _w((lambda *s: torch.randn(*s, dtype=torch.bfloat16) * 0.05)(B, S, D)),
            "W_gate": _w((lambda *s: torch.randn(*s, dtype=torch.bfloat16) * 0.4)(D, F) * (2.0 / D) ** 0.5),
            "W_up": _w((lambda *s: torch.randn(*s, dtype=torch.bfloat16) * 0.4)(D, F) * (2.0 / D) ** 0.5),
            "W_down": _w((lambda *s: torch.randn(*s, dtype=torch.bfloat16) * 0.4)(F, D) * (1.0 / F) ** 0.5),
        }
    _B_in = _B_setup()

    return {
        "A_x": _A_in["x"],
        "A_wqkv": _A_in["wqkv"],
        "A_wo": _A_in["wo"],
        "B_x": _B_in["x"],
        "B_W_gate": _B_in["W_gate"],
        "B_W_up": _B_in["W_up"],
        "B_W_down": _B_in["W_down"],
    }

def reference(A_x, A_wqkv, A_wo, B_x, B_W_gate, B_W_up, B_W_down):
    def _A_ref(x, wqkv, wo):
        B, S, D = x.shape
        H = 32; Dh = D // H
        qkv = (lambda x, *d: x.permute(*d))((x @ wqkv).reshape(B, S, 3, H, Dh), 2, 0, 3, 1, 4)
        q, k, v = qkv[0], qkv[1], qkv[2]
        scale = Dh ** -0.5
        scores = torch.einsum("bhqd,bhkd->bhqk", q, k) * scale
        p = _softmax(scores, axis=-1)
        o = torch.einsum("bhqk,bhkd->bhqd", p, v)
        return (lambda x, *d: x.permute(*d))(o, 0, 2, 1, 3).reshape(B, S, D) @ wo

    def _B_ref(x, W_gate, W_up, W_down):
        gate = torch.einsum("bsd,df->bsf", x, W_gate)
        up = torch.einsum("bsd,df->bsf", x, W_up)
        gate = gate * (lambda x, dt: x.to(dt))(gate > 0, gate.dtype)
        h = gate * up
        return torch.einsum("bsf,fd->bsd", h, W_down)

    x = A_x
    xn = _layernorm(x, axis=-1)
    return x + _A_ref(xn, A_wqkv, A_wo) + _B_ref(xn, B_W_gate, B_W_up, B_W_down)
```

```cpp
#include <cuda_runtime.h>
#include <cuda_bf16.h>
#include <cuda.h>
#include <stdint.h>

namespace {

constexpr int SEQ = 2048, DM = 512, FF = 1376, NH = 32;
constexpr int PLANE = 256 * 128;

constexpr int KV_BYTES = 131072;
constexpr int KV_OFF = NH * 2 * PLANE;
__device__ __align__(1024) uint8_t g_att[KV_OFF + NH * KV_BYTES];
constexpr int SLAB = 2048, H_SLABS = FF / 16, O_SLABS = DM / 16;
__device__ __align__(1024) uint8_t g_h[32 * H_SLABS * SLAB];
__device__ __align__(1024) uint8_t g_o[32 * O_SLABS * SLAB];
__device__ __align__(16) float g_nrm[3 * NH * 128];
__device__ float g_rr[SEQ];
struct Flags {
  unsigned int qkv;
  unsigned int done;
  unsigned int h[32];
  unsigned int o[32];
  unsigned int cs[16];
};
__device__ Flags g_flags;
constexpr int CS_N = 544;
__device__ __align__(16) float g_csp[8 * 16 * CS_N];

__device__ __forceinline__ uint32_t smem_u32(const void* p) { return (uint32_t)__cvta_generic_to_shared(p); }
__device__ __forceinline__ void wg_fence() { asm volatile("wgmma.fence.sync.aligned;" ::: "memory"); }
__device__ __forceinline__ void wg_commit() { asm volatile("wgmma.commit_group.sync.aligned;" ::: "memory"); }
template <int N> __device__ __forceinline__ void wg_wait() { asm volatile("wgmma.wait_group.sync.aligned %0;" ::"n"(N) : "memory"); }
__device__ __forceinline__ uint64_t mkdesc(uint32_t addr, uint32_t lbo, uint32_t sbo, uint32_t sw) {
  return (uint64_t)((addr & 0x3FFFF) >> 4) | ((uint64_t)(lbo >> 4) << 16) | ((uint64_t)(sbo >> 4) << 32) | ((uint64_t)sw << 62);
}
__device__ __forceinline__ void mbar_init(uint32_t bar, int cnt) { asm volatile("mbarrier.init.shared::cta.b64 [%0], %1;" ::"r"(bar), "r"(cnt) : "memory"); }
__device__ __forceinline__ void mbar_expect_tx(uint32_t bar, uint32_t bytes) { asm volatile("mbarrier.arrive.expect_tx.shared::cta.b64 _, [%0], %1;" ::"r"(bar), "r"(bytes) : "memory"); }
__device__ __forceinline__ void mbar_arrive(uint32_t bar) { asm volatile("mbarrier.arrive.shared::cta.b64 _, [%0];" ::"r"(bar) : "memory"); }
__device__ __forceinline__ void mbar_wait(uint32_t bar, uint32_t parity) {
  asm volatile("{\n.reg .pred p;\n.reg .u32 c;\n"
               "mbarrier.try_wait.parity.shared::cta.b64 p, [%0], %1;\n"
               "@p bra WAIT_DONE;\n"
               "mov.u32 c, 0;\n"
               "WAIT_LOOP:\n"
               "mbarrier.try_wait.parity.shared::cta.b64 p, [%0], %1, 20000;\n"
               "@p bra WAIT_DONE;\n"
               "add.u32 c, c, 1;\n"
               "setp.lt.u32 p, c, 0x10000;\n"
               "@p bra WAIT_LOOP;\n"
               "WAIT_DONE:\n}" ::"r"(bar), "r"(parity) : "memory");
}
__device__ __forceinline__ void mbar_spin(uint32_t bar, uint32_t parity) {
  asm volatile("{\n.reg .pred p;\n.reg .u32 c;\n"
               "mov.u32 c, 0;\n"
               "SPIN_LOOP:\n"
               "mbarrier.try_wait.parity.shared::cta.b64 p, [%0], %1;\n"
               "@p bra SPIN_DONE;\n"
               "add.u32 c, c, 1;\n"
               "setp.lt.u32 p, c, 0x400000;\n"
               "@p bra SPIN_LOOP;\n"
               "SPIN_DONE:\n}" ::"r"(bar), "r"(parity) : "memory");
}
__device__ __forceinline__ void bulk_g2s(uint32_t dst, const void* src, uint32_t bytes, uint32_t bar) {
  asm volatile("cp.async.bulk.shared::cluster.global.mbarrier::complete_tx::bytes [%0], [%1], %2, [%3];" ::"r"(dst), "l"(src), "r"(bytes), "r"(bar) : "memory");
}
__device__ __forceinline__ void tma_2d(uint32_t dst, const CUtensorMap* tm, int c0, int c1, uint32_t bar) {
  asm volatile("cp.async.bulk.tensor.2d.shared::cluster.global.mbarrier::complete_tx::bytes [%0], [%1, {%3, %4}], [%2];" ::"r"(dst), "l"(tm), "r"(bar), "r"(c0), "r"(c1) : "memory");
}
__device__ __forceinline__ void tma_prefetch_desc(const CUtensorMap* tm) { asm volatile("prefetch.tensormap [%0];" ::"l"(tm) : "memory"); }
__device__ __forceinline__ void fence_async_smem() { asm volatile("fence.proxy.async.shared::cta;" ::: "memory"); }
__device__ __forceinline__ void fence_mbar_init() { asm volatile("fence.mbarrier_init.release.cluster;" ::: "memory"); }
#define named_arrive(id, n) asm volatile("bar.arrive %0, %1;" ::"n"(id), "n"(n) : "memory")
#define named_bar(id, n) asm volatile("bar.sync %0, %1;" ::"n"(id), "n"(n) : "memory")
__device__ __forceinline__ float ex2(float x) { float y; asm volatile("ex2.approx.ftz.f32 %0, %1;" : "=f"(y) : "f"(x)); return y; }
__device__ __forceinline__ uint32_t pack_bf16(float lo, float hi) { uint32_t r; asm volatile("cvt.rn.bf16x2.f32 %0, %1, %2;" : "=r"(r) : "f"(hi), "f"(lo)); return r; }
__device__ __forceinline__ float2 lds_f2(uint32_t addr) { float2 v; asm("ld.shared.v2.f32 {%0, %1}, [%2];" : "=f"(v.x), "=f"(v.y) : "r"(addr)); return v; }
__device__ __forceinline__ float bf_lo(uint32_t v) { return __uint_as_float(v << 16); }
__device__ __forceinline__ float bf_hi(uint32_t v) { return __uint_as_float(v & 0xFFFF0000u); }
template <int N> __device__ __forceinline__ void reg_fence(float (&x)[N]) {
#pragma unroll
  for (int i = 0; i < N; i++) asm volatile("" : "+f"(x[i])::"memory");
}

__device__ __forceinline__ void mma_n192_t(float (&d)[96], uint64_t descA, uint64_t descB, int scaleD) {
  asm volatile("{\n.reg .pred p;\nsetp.ne.b32 p, %98, 0;\n"
    "wgmma.mma_async.sync.aligned.m64n192k16.f32.bf16.bf16 "
    "{%0, %1, %2, %3, %4, %5, %6, %7, %8, %9, %10, %11, %12, %13, %14, %15, %16, %17, %18, %19, %20, %21, %22, %23, %24, %25, %26, %27, %28, %29, %30, %31, %32, %33, %34, %35, %36, %37, %38, %39, %40, %41, %42, %43, %44, %45, %46, %47, %48, %49, %50, %51, %52, %53, %54, %55, %56, %57, %58, %59, %60, %61, %62, %63, %64, %65, %66, %67, %68, %69, %70, %71, %72, %73, %74, %75, %76, %77, %78, %79, %80, %81, %82, %83, %84, %85, %86, %87, %88, %89, %90, %91, %92, %93, %94, %95}, %96, %97, p, 1, 1, 0, 1;\n}\n"
    : "+f"(d[0]), "+f"(d[1]), "+f"(d[2]), "+f"(d[3]), "+f"(d[4]), "+f"(d[5]), "+f"(d[6]), "+f"(d[7]), "+f"(d[8]), "+f"(d[9]), "+f"(d[10]), "+f"(d[11]), "+f"(d[12]), "+f"(d[13]), "+f"(d[14]), "+f"(d[15]), "+f"(d[16]), "+f"(d[17]), "+f"(d[18]), "+f"(d[19]), "+f"(d[20]), "+f"(d[21]), "+f"(d[22]), "+f"(d[23]), "+f"(d[24]), "+f"(d[25]), "+f"(d[26]), "+f"(d[27]), "+f"(d[28]), "+f"(d[29]), "+f"(d[30]), "+f"(d[31]), "+f"(d[32]), "+f"(d[33]), "+f"(d[34]), "+f"(d[35]), "+f"(d[36]), "+f"(d[37]), "+f"(d[38]), "+f"(d[39]), "+f"(d[40]), "+f"(d[41]), "+f"(d[42]), "+f"(d[43]), "+f"(d[44]), "+f"(d[45]), "+f"(d[46]), "+f"(d[47]), "+f"(d[48]), "+f"(d[49]), "+f"(d[50]), "+f"(d[51]), "+f"(d[52]), "+f"(d[53]), "+f"(d[54]), "+f"(d[55]), "+f"(d[56]), "+f"(d[57]), "+f"(d[58]), "+f"(d[59]), "+f"(d[60]), "+f"(d[61]), "+f"(d[62]), "+f"(d[63]), "+f"(d[64]), "+f"(d[65]), "+f"(d[66]), "+f"(d[67]), "+f"(d[68]), "+f"(d[69]), "+f"(d[70]), "+f"(d[71]), "+f"(d[72]), "+f"(d[73]), "+f"(d[74]), "+f"(d[75]), "+f"(d[76]), "+f"(d[77]), "+f"(d[78]), "+f"(d[79]), "+f"(d[80]), "+f"(d[81]), "+f"(d[82]), "+f"(d[83]), "+f"(d[84]), "+f"(d[85]), "+f"(d[86]), "+f"(d[87]), "+f"(d[88]), "+f"(d[89]), "+f"(d[90]), "+f"(d[91]), "+f"(d[92]), "+f"(d[93]), "+f"(d[94]), "+f"(d[95])
    : "l"(descA), "l"(descB), "r"(scaleD));
}
__device__ __forceinline__ void mma_n176_rs(float (&d)[88], const uint32_t (&a)[4], uint64_t descB, int scaleD) {
  asm volatile("{\n.reg .pred p;\nsetp.ne.b32 p, %93, 0;\n"
    "wgmma.mma_async.sync.aligned.m64n176k16.f32.bf16.bf16 "
    "{%0, %1, %2, %3, %4, %5, %6, %7, %8, %9, %10, %11, %12, %13, %14, %15, %16, %17, %18, %19, %20, %21, %22, %23, %24, %25, %26, %27, %28, %29, %30, %31, %32, %33, %34, %35, %36, %37, %38, %39, %40, %41, %42, %43, %44, %45, %46, %47, %48, %49, %50, %51, %52, %53, %54, %55, %56, %57, %58, %59, %60, %61, %62, %63, %64, %65, %66, %67, %68, %69, %70, %71, %72, %73, %74, %75, %76, %77, %78, %79, %80, %81, %82, %83, %84, %85, %86, %87}, {%88, %89, %90, %91}, %92, p, 1, 1, 1;\n}\n"
    : "+f"(d[0]), "+f"(d[1]), "+f"(d[2]), "+f"(d[3]), "+f"(d[4]), "+f"(d[5]), "+f"(d[6]), "+f"(d[7]), "+f"(d[8]), "+f"(d[9]), "+f"(d[10]), "+f"(d[11]), "+f"(d[12]), "+f"(d[13]), "+f"(d[14]), "+f"(d[15]), "+f"(d[16]), "+f"(d[17]), "+f"(d[18]), "+f"(d[19]), "+f"(d[20]), "+f"(d[21]), "+f"(d[22]), "+f"(d[23]), "+f"(d[24]), "+f"(d[25]), "+f"(d[26]), "+f"(d[27]), "+f"(d[28]), "+f"(d[29]), "+f"(d[30]), "+f"(d[31]), "+f"(d[32]), "+f"(d[33]), "+f"(d[34]), "+f"(d[35]), "+f"(d[36]), "+f"(d[37]), "+f"(d[38]), "+f"(d[39]), "+f"(d[40]), "+f"(d[41]), "+f"(d[42]), "+f"(d[43]), "+f"(d[44]), "+f"(d[45]), "+f"(d[46]), "+f"(d[47]), "+f"(d[48]), "+f"(d[49]), "+f"(d[50]), "+f"(d[51]), "+f"(d[52]), "+f"(d[53]), "+f"(d[54]), "+f"(d[55]), "+f"(d[56]), "+f"(d[57]), "+f"(d[58]), "+f"(d[59]), "+f"(d[60]), "+f"(d[61]), "+f"(d[62]), "+f"(d[63]), "+f"(d[64]), "+f"(d[65]), "+f"(d[66]), "+f"(d[67]), "+f"(d[68]), "+f"(d[69]), "+f"(d[70]), "+f"(d[71]), "+f"(d[72]), "+f"(d[73]), "+f"(d[74]), "+f"(d[75]), "+f"(d[76]), "+f"(d[77]), "+f"(d[78]), "+f"(d[79]), "+f"(d[80]), "+f"(d[81]), "+f"(d[82]), "+f"(d[83]), "+f"(d[84]), "+f"(d[85]), "+f"(d[86]), "+f"(d[87])
    : "r"(a[0]), "r"(a[1]), "r"(a[2]), "r"(a[3]), "l"(descB), "r"(scaleD));
}
__device__ __forceinline__ void mma_n128_t(float (&d)[64], uint64_t descA, uint64_t descB, int scaleD) {
  asm volatile("{\n.reg .pred p;\nsetp.ne.b32 p, %66, 0;\n"
    "wgmma.mma_async.sync.aligned.m64n128k16.f32.bf16.bf16 "
    "{%0, %1, %2, %3, %4, %5, %6, %7, %8, %9, %10, %11, %12, %13, %14, %15, %16, %17, %18, %19, %20, %21, %22, %23, %24, %25, %26, %27, %28, %29, %30, %31, %32, %33, %34, %35, %36, %37, %38, %39, %40, %41, %42, %43, %44, %45, %46, %47, %48, %49, %50, %51, %52, %53, %54, %55, %56, %57, %58, %59, %60, %61, %62, %63}, %64, %65, p, 1, 1, 0, 1;\n}\n"
    : "+f"(d[0]), "+f"(d[1]), "+f"(d[2]), "+f"(d[3]), "+f"(d[4]), "+f"(d[5]), "+f"(d[6]), "+f"(d[7]), "+f"(d[8]), "+f"(d[9]), "+f"(d[10]), "+f"(d[11]), "+f"(d[12]), "+f"(d[13]), "+f"(d[14]), "+f"(d[15]), "+f"(d[16]), "+f"(d[17]), "+f"(d[18]), "+f"(d[19]), "+f"(d[20]), "+f"(d[21]), "+f"(d[22]), "+f"(d[23]), "+f"(d[24]), "+f"(d[25]), "+f"(d[26]), "+f"(d[27]), "+f"(d[28]), "+f"(d[29]), "+f"(d[30]), "+f"(d[31]), "+f"(d[32]), "+f"(d[33]), "+f"(d[34]), "+f"(d[35]), "+f"(d[36]), "+f"(d[37]), "+f"(d[38]), "+f"(d[39]), "+f"(d[40]), "+f"(d[41]), "+f"(d[42]), "+f"(d[43]), "+f"(d[44]), "+f"(d[45]), "+f"(d[46]), "+f"(d[47]), "+f"(d[48]), "+f"(d[49]), "+f"(d[50]), "+f"(d[51]), "+f"(d[52]), "+f"(d[53]), "+f"(d[54]), "+f"(d[55]), "+f"(d[56]), "+f"(d[57]), "+f"(d[58]), "+f"(d[59]), "+f"(d[60]), "+f"(d[61]), "+f"(d[62]), "+f"(d[63])
    : "l"(descA), "l"(descB), "r"(scaleD));
}
__device__ __forceinline__ void qk_n64(float (&d)[32], uint32_t a0, uint32_t a1, uint32_t a2, uint32_t a3, uint64_t descB) {
  asm volatile("wgmma.mma_async.sync.aligned.m64n64k16.f32.bf16.bf16 "
    "{%0, %1, %2, %3, %4, %5, %6, %7, %8, %9, %10, %11, %12, %13, %14, %15, %16, %17, %18, %19, %20, %21, %22, %23, %24, %25, %26, %27, %28, %29, %30, %31}, {%32, %33, %34, %35}, %36, 0, 1, 1, 0;\n"
    : "=f"(d[0]), "=f"(d[1]), "=f"(d[2]), "=f"(d[3]), "=f"(d[4]), "=f"(d[5]), "=f"(d[6]), "=f"(d[7]), "=f"(d[8]), "=f"(d[9]), "=f"(d[10]), "=f"(d[11]), "=f"(d[12]), "=f"(d[13]), "=f"(d[14]), "=f"(d[15]), "=f"(d[16]), "=f"(d[17]), "=f"(d[18]), "=f"(d[19]), "=f"(d[20]), "=f"(d[21]), "=f"(d[22]), "=f"(d[23]), "=f"(d[24]), "=f"(d[25]), "=f"(d[26]), "=f"(d[27]), "=f"(d[28]), "=f"(d[29]), "=f"(d[30]), "=f"(d[31])
    : "r"(a0), "r"(a1), "r"(a2), "r"(a3), "l"(descB));
}
__device__ __forceinline__ void qk_n128(float (&d)[64], uint32_t a0, uint32_t a1, uint32_t a2, uint32_t a3, uint64_t descB) {
  asm volatile("wgmma.mma_async.sync.aligned.m64n128k16.f32.bf16.bf16 "
    "{%0, %1, %2, %3, %4, %5, %6, %7, %8, %9, %10, %11, %12, %13, %14, %15, %16, %17, %18, %19, %20, %21, %22, %23, %24, %25, %26, %27, %28, %29, %30, %31, %32, %33, %34, %35, %36, %37, %38, %39, %40, %41, %42, %43, %44, %45, %46, %47, %48, %49, %50, %51, %52, %53, %54, %55, %56, %57, %58, %59, %60, %61, %62, %63}, {%64, %65, %66, %67}, %68, 0, 1, 1, 0;\n"
    : "=f"(d[0]), "=f"(d[1]), "=f"(d[2]), "=f"(d[3]), "=f"(d[4]), "=f"(d[5]), "=f"(d[6]), "=f"(d[7]), "=f"(d[8]), "=f"(d[9]), "=f"(d[10]), "=f"(d[11]), "=f"(d[12]), "=f"(d[13]), "=f"(d[14]), "=f"(d[15]), "=f"(d[16]), "=f"(d[17]), "=f"(d[18]), "=f"(d[19]), "=f"(d[20]), "=f"(d[21]), "=f"(d[22]), "=f"(d[23]), "=f"(d[24]), "=f"(d[25]), "=f"(d[26]), "=f"(d[27]), "=f"(d[28]), "=f"(d[29]), "=f"(d[30]), "=f"(d[31]), "=f"(d[32]), "=f"(d[33]), "=f"(d[34]), "=f"(d[35]), "=f"(d[36]), "=f"(d[37]), "=f"(d[38]), "=f"(d[39]), "=f"(d[40]), "=f"(d[41]), "=f"(d[42]), "=f"(d[43]), "=f"(d[44]), "=f"(d[45]), "=f"(d[46]), "=f"(d[47]), "=f"(d[48]), "=f"(d[49]), "=f"(d[50]), "=f"(d[51]), "=f"(d[52]), "=f"(d[53]), "=f"(d[54]), "=f"(d[55]), "=f"(d[56]), "=f"(d[57]), "=f"(d[58]), "=f"(d[59]), "=f"(d[60]), "=f"(d[61]), "=f"(d[62]), "=f"(d[63])
    : "r"(a0), "r"(a1), "r"(a2), "r"(a3), "l"(descB));
}
__device__ __forceinline__ void qki_n128(float (&d)[64], uint32_t a0, uint32_t a1, uint32_t a2, uint32_t a3, uint64_t descB) {
  asm volatile("wgmma.mma_async.sync.aligned.m64n128k16.f32.bf16.bf16 "
    "{%0, %1, %2, %3, %4, %5, %6, %7, %8, %9, %10, %11, %12, %13, %14, %15, %16, %17, %18, %19, %20, %21, %22, %23, %24, %25, %26, %27, %28, %29, %30, %31, %32, %33, %34, %35, %36, %37, %38, %39, %40, %41, %42, %43, %44, %45, %46, %47, %48, %49, %50, %51, %52, %53, %54, %55, %56, %57, %58, %59, %60, %61, %62, %63}, {%64, %65, %66, %67}, %68, 0, 1, 1, 0;\n"
    : "+f"(d[0]), "+f"(d[1]), "+f"(d[2]), "+f"(d[3]), "+f"(d[4]), "+f"(d[5]), "+f"(d[6]), "+f"(d[7]), "+f"(d[8]), "+f"(d[9]), "+f"(d[10]), "+f"(d[11]), "+f"(d[12]), "+f"(d[13]), "+f"(d[14]), "+f"(d[15]), "+f"(d[16]), "+f"(d[17]), "+f"(d[18]), "+f"(d[19]), "+f"(d[20]), "+f"(d[21]), "+f"(d[22]), "+f"(d[23]), "+f"(d[24]), "+f"(d[25]), "+f"(d[26]), "+f"(d[27]), "+f"(d[28]), "+f"(d[29]), "+f"(d[30]), "+f"(d[31]), "+f"(d[32]), "+f"(d[33]), "+f"(d[34]), "+f"(d[35]), "+f"(d[36]), "+f"(d[37]), "+f"(d[38]), "+f"(d[39]), "+f"(d[40]), "+f"(d[41]), "+f"(d[42]), "+f"(d[43]), "+f"(d[44]), "+f"(d[45]), "+f"(d[46]), "+f"(d[47]), "+f"(d[48]), "+f"(d[49]), "+f"(d[50]), "+f"(d[51]), "+f"(d[52]), "+f"(d[53]), "+f"(d[54]), "+f"(d[55]), "+f"(d[56]), "+f"(d[57]), "+f"(d[58]), "+f"(d[59]), "+f"(d[60]), "+f"(d[61]), "+f"(d[62]), "+f"(d[63])
    : "r"(a0), "r"(a1), "r"(a2), "r"(a3), "l"(descB));
}
__device__ __forceinline__ void pv_n24(float (&d)[12], uint32_t a0, uint32_t a1, uint32_t a2, uint32_t a3, uint64_t descB) {
  asm volatile("wgmma.mma_async.sync.aligned.m64n24k16.f32.bf16.bf16 "
    "{%0, %1, %2, %3, %4, %5, %6, %7, %8, %9, %10, %11}, {%12, %13, %14, %15}, %16, 1, 1, 1, 1;\n"
    : "+f"(d[0]), "+f"(d[1]), "+f"(d[2]), "+f"(d[3]), "+f"(d[4]), "+f"(d[5]), "+f"(d[6]), "+f"(d[7]), "+f"(d[8]), "+f"(d[9]), "+f"(d[10]), "+f"(d[11])
    : "r"(a0), "r"(a1), "r"(a2), "r"(a3), "l"(descB));
}

__device__ __forceinline__ void flag_wait(const unsigned int* p, unsigned int target) {
  unsigned int v, spins = 0;
  do {
    asm volatile("ld.acquire.gpu.global.u32 %0, [%1];" : "=r"(v) : "l"(p) : "memory");
  } while (v < target && ++spins < (1u << 22));
}
__device__ __forceinline__ void flag_add(unsigned int* p) { asm volatile("red.relaxed.gpu.global.add.u32 [%0], 1;" ::"l"(p) : "memory"); }
__device__ __forceinline__ void fence_gpu() { asm volatile("fence.acq_rel.gpu;" ::: "memory"); }

constexpr int P1_STAGES = 4, P1_STAGE_BYTES = 24576, P1_RING_OFF = 131072;
constexpr int P2_PART_OFF = 81920, P2_KV_OFF = 98304, ONES_OFF = P2_KV_OFF + KV_BYTES;
constexpr int DN_STAGES = 3, DN_BYTES = 24576;
constexpr int CS_OFF = ONES_OFF;
constexpr int BAR_OFF = ONES_OFF + CS_N * 4;
constexpr int SMEM_BYTES = BAR_OFF + 368;
static_assert(SMEM_BYTES <= 232448 && BAR_OFF % 8 == 0, "shared memory");
constexpr int B_FULL = 0, B_EMPTY = 4, B_X = 8, B_KV = 16, B_DNF = 25, B_DNE = 28, B_WO = 31, B_CS = 39, B_ONES = 41, B_S8 = 42, B_SL = 43;
constexpr float QSCALE = 0.25f * 1.4426950408889634f;

struct Params {
  CUtensorMap x, wqkv, wqkv32, wg, wu, wo, wd, out;
};

struct AttnPre { uint32_t q0, q1, q2, q3; uint4 kn, vn; uint32_t qu; };
__device__ __forceinline__ AttnPre attn_prefetch(int wg, int warp, int lane, int bid) {
  const int head = bid >> 2, qq = bid & 3;
  AttnPre p;
  const uint8_t* qb = g_att + (size_t)head * 2 * PLANE + (qq * 64 + warp * 2) * 128 + lane * 4 + wg * 3 * 1024;
  p.q0 = *reinterpret_cast<const uint32_t*>(qb);
  p.q1 = *reinterpret_cast<const uint32_t*>(qb + 128);
  p.q2 = *reinterpret_cast<const uint32_t*>(qb + PLANE);
  p.q3 = *reinterpret_cast<const uint32_t*>(qb + PLANE + 128);
  p.kn = *reinterpret_cast<const uint4*>(g_nrm + (NH + head) * 128 + lane * 4);
  p.vn = *reinterpret_cast<const uint4*>(g_nrm + (2 * NH + head) * 128 + lane * 4);
  p.qu = __float_as_uint(g_nrm[head * 128 + qq * 32 + lane]);
  return p;
}

__device__ __forceinline__ void phase1_mma(uint8_t* smem, uint32_t sb, int wg, int warp, int lane, int tid, int bid, AttnPre& pre) {
  const int rb = bid >> 3, cg = bid & 7;
  const uint32_t sA = sb, sB = sb + P1_RING_OFF, bars = sb + BAR_OFF;
  float rstd0, rstd1;
  uint32_t eoff[12];
#pragma unroll
  for (int hh = 0; hh < 12; hh++) {
    const int gh = cg * 12 + hh, type = gh >> 5, head = gh & 31;
    const uint32_t o0 = type == 0 ? head * (2 * PLANE) + rb * 2048 : KV_OFF + head * KV_BYTES + rb * 4096 + (type == 1 ? 2048 : 0);
    const uint32_t o1 = type == 0 ? head * (2 * PLANE) + rb * 2048 + PLANE : KV_OFF + head * KV_BYTES + rb * 2048 + (type == 1 ? 98304 : 65536);
    eoff[hh] = (lane < 16 ? o0 : o1) + warp * 256 + (lane & 15) * 16;
    asm volatile("" : "+r"(eoff[hh]));
  }
  const uint64_t dA0 = mkdesc(sA + wg * 8192, 16, 1024, 1);
  const int g = lane >> 2, c4 = lane & 3;
  float mean0, mean1;
  int it = 0;
  {
    float acc[96];
    float s0 = 0.f, s1 = 0.f, q0 = 0.f, q1 = 0.f;
    const uint8_t* xrow = smem + (warp * 16 + g) * 128 + ((c4 + 4 * (g & 1)) << 4);
#pragma unroll 1
    for (; it < 8; it++) {
      const int s = it % P1_STAGES, kc = it;
      mbar_spin(bars + 8 * (B_X + it), 0);
      mbar_spin(bars + 8 * (B_FULL + s), (it / P1_STAGES) & 1);
      const uint64_t dB = mkdesc(sB + s * P1_STAGE_BYTES, 8192, 1024, 1);
      const uint64_t dA = dA0 + (uint64_t)(kc * 1024);
      wg_fence();
#pragma unroll
      for (int kk = 0; kk < 4; kk++) mma_n192_t(acc, dA + kk * 2, dB + kk * 128, kk > 0 || it > 0);
      wg_commit();
      {
        const uint8_t* xp = xrow + kc * 16384;
        const uint4 u[4] = {*reinterpret_cast<const uint4*>(xp), *reinterpret_cast<const uint4*>(xp + (64 - 128 * (g & 1))),
                            *reinterpret_cast<const uint4*>(xp + 1024), *reinterpret_cast<const uint4*>(xp + 1024 + (64 - 128 * (g & 1)))};
#pragma unroll
        for (int i = 0; i < 4; i++) {
          const uint32_t w[4] = {u[i].x, u[i].y, u[i].z, u[i].w};
#pragma unroll
          for (int e = 0; e < 4; e++) {
            const float lo = bf_lo(w[e]), hi = bf_hi(w[e]);
            if (i < 2) { s0 += lo + hi; q0 = fmaf(lo, lo, fmaf(hi, hi, q0)); }
            else { s1 += lo + hi; q1 = fmaf(lo, lo, fmaf(hi, hi, q1)); }
          }
        }
      }
      wg_wait<0>();
      if (lane == 0 && it < 7) mbar_arrive(bars + 8 * (B_EMPTY + s));
    }
    reg_fence(acc);
    s0 += __shfl_xor_sync(0xffffffffu, s0, 1); s1 += __shfl_xor_sync(0xffffffffu, s1, 1);
    q0 += __shfl_xor_sync(0xffffffffu, q0, 1); q1 += __shfl_xor_sync(0xffffffffu, q1, 1);
    s0 += __shfl_xor_sync(0xffffffffu, s0, 2); s1 += __shfl_xor_sync(0xffffffffu, s1, 2);
    q0 += __shfl_xor_sync(0xffffffffu, q0, 2); q1 += __shfl_xor_sync(0xffffffffu, q1, 2);
    mean0 = s0 * (1.f / DM); mean1 = s1 * (1.f / DM);
    rstd0 = rsqrtf(fmaxf(q0 * (1.f / DM) - mean0 * mean0, 0.f) + 1e-5f);
    rstd1 = rsqrtf(fmaxf(q1 * (1.f / DM) - mean1 * mean1, 0.f) + 1e-5f);
    named_bar(12, 384);
    uint32_t csa = sb + CS_OFF + c4 * 8;
    asm volatile("" : "+r"(csa)::"memory");
    const uint32_t scratch = sB + (7 % P1_STAGES) * P1_STAGE_BYTES + warp * 3072 + lane * 16;
    float nn[12];
#pragma unroll
    for (int hh = 0; hh < 12; hh++) {
      const float qs = (cg * 12 + hh) < NH ? QSCALE : 1.0f;
      const float sc0 = rstd0 * qs, sc1 = rstd1 * qs;
      const float2 ca = lds_f2(csa + hh * 64), cb = lds_f2(csa + hh * 64 + 32);
      const float a0 = fmaf(-mean0, ca.x, acc[8 * hh]) * sc0, a1 = fmaf(-mean0, ca.y, acc[8 * hh + 1]) * sc0;
      const float a2 = fmaf(-mean1, ca.x, acc[8 * hh + 2]) * sc1, a3 = fmaf(-mean1, ca.y, acc[8 * hh + 3]) * sc1;
      const float b0 = fmaf(-mean0, cb.x, acc[8 * hh + 4]) * sc0, b1 = fmaf(-mean0, cb.y, acc[8 * hh + 5]) * sc0;
      const float b2 = fmaf(-mean1, cb.x, acc[8 * hh + 6]) * sc1, b3 = fmaf(-mean1, cb.y, acc[8 * hh + 7]) * sc1;
      asm volatile("stmatrix.sync.aligned.m8n8.x4.shared.b16 [%0], {%1, %2, %3, %4};" ::"r"(scratch + (hh % 6) * 512), "r"(pack_bf16(a0, a1)), "r"(pack_bf16(a2, a3)), "r"(pack_bf16(b0, b1)), "r"(pack_bf16(b2, b3)) : "memory");
      if (hh % 6 == 5) {
        __syncwarp();
        uint4 v[6];
#pragma unroll
        for (int i = 0; i < 6; i++)
          asm volatile("ld.shared.v4.b32 {%0, %1, %2, %3}, [%4];" : "=r"(v[i].x), "=r"(v[i].y), "=r"(v[i].z), "=r"(v[i].w) : "r"(scratch + i * 512) : "memory");
#pragma unroll
        for (int i = 0; i < 6; i++)
          asm volatile("st.global.v4.b32 [%0], {%1, %2, %3, %4};" ::"l"(g_att + eoff[hh - 5 + i]), "r"(v[i].x), "r"(v[i].y), "r"(v[i].z), "r"(v[i].w));
        __syncwarp();
      }
      const float n0 = fmaf(a0, a0, fmaf(a1, a1, fmaf(b0, b0, b1 * b1)));
      const float n1 = fmaf(a2, a2, fmaf(a3, a3, fmaf(b2, b2, b3 * b3)));
      nn[hh] = __uint_as_float(max(__float_as_uint(n0), __float_as_uint(n1)));
    }
#pragma unroll
    for (int hh = 0; hh < 12; hh++) nn[hh] += __shfl_xor_sync(0xffffffffu, nn[hh], 1);
#pragma unroll
    for (int hh = 0; hh < 12; hh++) nn[hh] += __shfl_xor_sync(0xffffffffu, nn[hh], 2);
    unsigned int mine = 0;
#pragma unroll
    for (int hh = 0; hh < 12; hh++) {
      const unsigned int m = __reduce_max_sync(0xffffffffu, __float_as_uint(nn[hh]));
      if (lane == hh) mine = m;
    }
    if (lane == 0) mbar_arrive(bars + 8 * (B_EMPTY + 7 % P1_STAGES));
    if (lane < 12) g_nrm[(cg * 12 + lane) * 128 + rb * 8 + warp] = __uint_as_float(mine);
    if (wg == 0) named_arrive(10, 160); else named_arrive(11, 160);
  }
  {
    float ag[88], au[88];
    const int lrow = ((lane >> 3) & 1) * 8 + (lane & 7), lun = lane >> 4;
    const uint32_t arow = sA + (warp * 16 + lrow) * 128;
#pragma unroll 1
    for (; it < 24; it++) {
      const int s = it % P1_STAGES, i2 = (it - 8 + rb) & 15;
      uint32_t af[2][4];
#pragma unroll
      for (int kk = 0; kk < 2; kk++) {
        const uint32_t addr = arow + (i2 >> 1) * 16384 + (((((i2 & 1) * 2 + kk) * 2 + lun) ^ (lrow & 7)) << 4);
        asm volatile("ldmatrix.sync.aligned.m8n8.x4.shared.b16 {%0, %1, %2, %3}, [%4];" : "=r"(af[kk][0]), "=r"(af[kk][1]), "=r"(af[kk][2]), "=r"(af[kk][3]) : "r"(addr));
      }
      mbar_spin(bars + 8 * (B_FULL + s), (it / P1_STAGES) & 1);
      if (it == 8 && tid == 0) mbar_arrive(bars + 8 * B_S8);
      const uint64_t dB = mkdesc(sB + s * P1_STAGE_BYTES, 4096, 1024, 1);
      wg_fence();
#pragma unroll
      for (int kk = 0; kk < 2; kk++) {
        mma_n176_rs(ag, af[kk], dB + kk * 128, kk > 0 || it > 8);
        mma_n176_rs(au, af[kk], dB + 768 + kk * 128, kk > 0 || it > 8);
      }
      wg_commit();
      wg_wait<0>();
      if (lane == 0) mbar_arrive(bars + 8 * (B_EMPTY + s));
    }
    reg_fence(ag); reg_fence(au);
    named_bar(9, 416);
    pre = attn_prefetch(wg, warp & 3, lane, bid);
    named_bar(13, 384);
    uint32_t csa = sb + CS_OFF + c4 * 8;
    asm volatile("" : "+r"(csa)::"memory");
    if (cg == 0 && c4 == 0) { g_rr[rb * 128 + warp * 16 + g] = rstd0 * rstd0; g_rr[rb * 128 + warp * 16 + g + 8] = rstd1 * rstd1; }
    uint32_t hp[44];
#pragma unroll
    for (int j = 0; j < 22; j++) {
      const float2 cgt = lds_f2(csa + (192 + 8 * j) * 4), cup = lds_f2(csa + (368 + 8 * j) * 4);
      float h[4];
#pragma unroll
      for (int e = 0; e < 4; e++) {
        const float nm = e < 2 ? -mean0 : -mean1;
        h[e] = fmaxf(fmaf(nm, (e & 1) ? cgt.y : cgt.x, ag[4 * j + e]), 0.f) * fmaf(nm, (e & 1) ? cup.y : cup.x, au[4 * j + e]);
      }
      hp[2 * j] = pack_bf16(h[0], h[1]);
      hp[2 * j + 1] = pack_bf16(h[2], h[3]);
    }
    asm volatile("setmaxnreg.dec.sync.aligned.u32 128;");
    const uint32_t hst = sb + wg * (11 * SLAB) + ((warp & 3) * 2 + ((lane >> 3) & 1)) * 256 + (lane >> 4) * 128 + (lane & 7) * 16;
#pragma unroll
    for (int sl = 0; sl < 11; sl++)
      asm volatile("stmatrix.sync.aligned.m8n8.x4.shared.b16 [%0], {%1, %2, %3, %4};" ::"r"(hst + sl * SLAB), "r"(hp[4 * sl]), "r"(hp[4 * sl + 1]), "r"(hp[4 * sl + 2]), "r"(hp[4 * sl + 3]) : "memory");
    fence_async_smem();
    named_arrive(8, 384);
  }
}

__device__ __forceinline__ void phase1_load_w(uint32_t sb, const Params& P, int rb, int cg, int it) {
  const int s = it % P1_STAGES;
  const uint32_t dst = sb + P1_RING_OFF + s * P1_STAGE_BYTES, bar = sb + BAR_OFF + 8 * (B_FULL + s);
  mbar_expect_tx(bar, P1_STAGE_BYTES);
  if (it < 8) {
#pragma unroll
    for (int nb = 0; nb < 3; nb++) tma_2d(dst + nb * 8192, &P.wqkv, cg * 192 + nb * 64, it * 64, bar);
  } else {
    const int k0 = ((it - 8 + rb) & 15) * 32;
#pragma unroll
    for (int nb = 0; nb < 3; nb++) {
      tma_2d(dst + nb * 4096, &P.wg, cg * 176 + nb * 64, k0, bar);
      tma_2d(dst + 12288 + nb * 4096, &P.wu, cg * 176 + nb * 64, k0, bar);
    }
  }
}
__device__ __forceinline__ void phase1_load_x(uint32_t sb, const Params& P, int rb, int kc) {
  const uint32_t bar = sb + BAR_OFF + 8 * (B_X + kc);
  mbar_expect_tx(bar, 16384);
  tma_2d(sb + kc * 16384, &P.x, kc * 64, rb * 128, bar);
}
__device__ __forceinline__ void phase1_first_loads(uint32_t sb, const Params& P, int rb, int cg) {
  phase1_load_w(sb, P, rb, cg, 0);
  phase1_load_x(sb, P, rb, 0);
}
__device__ __forceinline__ void phase1_producer(uint32_t sb, const Params& P, int rb, int cg) {
  const uint32_t bars = sb + BAR_OFF;
  tma_prefetch_desc(&P.wqkv32);
#pragma unroll
  for (int it = 1; it < P1_STAGES; it++) {
    phase1_load_w(sb, P, rb, cg, it); phase1_load_x(sb, P, rb, it);
    if (it == 2) {
      mbar_expect_tx(bars + 8 * B_SL, 12288);
#pragma unroll
      for (int nb = 0; nb < 3; nb++) tma_2d(sb + 7 * 16384 + nb * 4096, &P.wqkv32, cg * 192 + nb * 64, rb * 32, bars + 8 * B_SL);
    }
  }
  tma_prefetch_desc(&P.wg); tma_prefetch_desc(&P.wu);
#pragma unroll
  for (int kc = P1_STAGES; kc < 7; kc++) phase1_load_x(sb, P, rb, kc);
#pragma unroll 1
  for (int it = P1_STAGES; it < 24; it++) {
    mbar_spin(bars + 8 * (B_EMPTY + it % P1_STAGES), ((it / P1_STAGES) - 1) & 1);
    if (it == 12) mbar_wait(bars + 8 * (B_CS + 1), 0);
    phase1_load_w(sb, P, rb, cg, it);
    if (it == 5) {
      mbar_wait(bars + 8 * B_CS, 0);
      phase1_load_x(sb, P, rb, 7);
    }
  }
}

__device__ __forceinline__ void colsum_slice(const uint8_t* tile, int box_stride, int npairs, float* dst, int t) {
  if (t < npairs) {
    const uint8_t* p = tile + (t >> 5) * box_stride + (t & 3) * 4;
    const int chunk = (t & 31) >> 2;
    float a0 = 0.f, a1 = 0.f, b0 = 0.f, b1 = 0.f;
#pragma unroll
    for (int k = 0; k < 32; k += 2) {
      const uint32_t u = *reinterpret_cast<const uint32_t*>(p + k * 128 + ((chunk ^ (k & 7)) << 4));
      const uint32_t v = *reinterpret_cast<const uint32_t*>(p + (k + 1) * 128 + ((chunk ^ ((k + 1) & 7)) << 4));
      a0 += bf_lo(u); a1 += bf_hi(u); b0 += bf_lo(v); b1 += bf_hi(v);
    }
    *reinterpret_cast<float2*>(dst + 2 * t) = make_float2(a0 + b0, a1 + b1);
  }
  __syncwarp();
}
__device__ __forceinline__ void colsum_gather(uint8_t* smem, const float* src, int first, int n, int t) {
  for (int c = first + t; c < first + n; c += 128) {
    float a = 0.f;
#pragma unroll
    for (int r = 0; r < 16; r++) a += __ldcg(src + r * CS_N + c);
    reinterpret_cast<float*>(smem + CS_OFF)[c] = a;
  }
}

__device__ __forceinline__ uint32_t exp2_pair_poly(float t0, float t1, uint32_t cmask, uint32_t ca2) {
  uint32_t r;
  asm volatile("{\n.reg .f32 z0, z1;\n.reg .b32 L, x, g, c;\n"
               "add.rn.f32 z0, %1, 0f47C08280;\n"
               "add.rn.f32 z1, %2, 0f47C08280;\n"
               "prmt.b32 L, z0, z1, 0x5410;\n"
               "lop3.b32 x, L, %3, 0x3F803F80, 0xEA;\n"
               "fma.rn.bf16x2 g, %4, x, %5;\n"
               "fma.rn.bf16x2 c, g, x, %6;\n"
               "sub.u32 %0, L, c;\n}"
               : "=r"(r) : "f"(t0), "f"(t1), "r"(cmask), "r"(ca2), "r"(0x43044304u), "r"(0x421e421eu));
  return r;
}
#define SPLIT2 11
#define SPLIT5 6
#define NPOLY 20
__host__ __device__ constexpr bool is_poly(int p) { return ((p + 1) * NPOLY / 32) != (p * NPOLY / 32); }

template <int OFF, int SG>
__device__ __forceinline__ void exp_seg64(uint32_t (&P)[8], const float (&S)[64], uint32_t cmask, uint32_t ca2) {
#pragma unroll
  for (int p = 0; p < 8; p++) {
    if (is_poly(SG * 8 + p)) P[p] = exp2_pair_poly(S[OFF + 2 * p], S[OFF + 2 * p + 1], cmask, ca2);
    else P[p] = pack_bf16(ex2(S[OFF + 2 * p]), ex2(S[OFF + 2 * p + 1]));
  }
}

constexpr uint64_t DK_STEP = 256ull - (128ull << 16);
constexpr uint64_t DV_STEP = 256ull - (128ull << 32);

template <bool WAIT>
__device__ __forceinline__ void attn_segment(float (&O)[12], uint32_t q0, uint32_t q1, uint32_t q2, uint32_t q3, uint64_t dK, uint64_t dV,
                                             int t0, int t1, uint32_t sKV, uint32_t cmask, uint32_t ca2) {
  float S[64];
  uint32_t PX[8], PY[8];
  if (WAIT) mbar_wait(sKV + 8 * (t0 >> 1), 0);
  wg_fence();
  qk_n128(S, q0, q1, q2, q3, dK);
  wg_commit();
  wg_wait<0>();
#pragma unroll 1
  for (int t = t0; t < t1; t++) {
    reg_fence(S);
    exp_seg64<0, 0>(PX, S, cmask, ca2);
    wg_fence();
    pv_n24(O, PX[0], PX[1], PX[2], PX[3], dV);
    pv_n24(O, PX[4], PX[5], PX[6], PX[7], dV + 16);
    wg_commit();
    exp_seg64<16, 1>(PY, S, cmask, ca2);
    wg_fence();
    pv_n24(O, PY[0], PY[1], PY[2], PY[3], dV + 32);
    pv_n24(O, PY[4], PY[5], PY[6], PY[7], dV + 48);
    wg_commit();
    wg_wait<1>();
    exp_seg64<32, 2>(PX, S, cmask, ca2);
    wg_fence();
    pv_n24(O, PX[0], PX[1], PX[2], PX[3], dV + 64);
    pv_n24(O, PX[4], PX[5], PX[6], PX[7], dV + 80);
    wg_commit();
    wg_wait<1>();
    exp_seg64<48, 3>(PY, S, cmask, ca2);
    if (WAIT) mbar_wait(sKV + 8 * ((t + 1) >> 1), 0);
    dK += DK_STEP;
    wg_fence();
    pv_n24(O, PY[0], PY[1], PY[2], PY[3], dV + 96);
    pv_n24(O, PY[4], PY[5], PY[6], PY[7], dV + 112);
    qki_n128(S, q0, q1, q2, q3, dK);
    wg_commit();
    wg_wait<0>();
    dV += DV_STEP;
  }
}

__device__ __forceinline__ void attention(uint8_t* smem, uint32_t sb, int wg, int warp, int lane, int tid, int bid, const AttnPre& pre) {
  const uint32_t sKV = sb + BAR_OFF + 8 * B_KV, kvb = sb + P2_KV_OFF;
  const int head = bid >> 2, qq = bid & 3;
  const uint8_t* qbase = g_att + (size_t)head * 2 * PLANE + (qq * 64 + warp * 2) * 128 + lane * 4;
  uint32_t qn0 = pre.q0, qn1 = pre.q1, qn2 = pre.q2, qn3 = pre.q3;
  bool fast;
  {
    const unsigned int ku = __reduce_max_sync(0xffffffffu, max(max(pre.kn.x, pre.kn.y), max(pre.kn.z, pre.kn.w)));
    const unsigned int vu = __reduce_max_sync(0xffffffffu, max(max(pre.vn.x, pre.vn.y), max(pre.vn.z, pre.vn.w)));
    const unsigned int qu = __reduce_max_sync(0xffffffffu, pre.qu);
    fast = (__uint_as_float(qu) * __uint_as_float(ku) <= 3600.f) && (__uint_as_float(vu) <= 1.0e24f);
  }
  const uint64_t dK0 = mkdesc(kvb + 2048, 96256, 128, 0);
  const uint64_t dV0 = mkdesc(kvb, 128, 65536, 0);
  uint32_t cmask = 0x007F007Fu, ca2 = 0xc22fc22fu;
  asm volatile("" : "+r"(cmask), "+r"(ca2));
  const int nseg = fast ? (wg == 1 ? 4 : 3) : (wg == 2 ? 2 : 3);
  auto seg_qt = [&](int sg) {
    if (!fast || wg == 0) return 3 * wg + sg;
    if (wg == 1) return sg == 0 ? 3 : (sg == 1 ? 2 : (sg == 2 ? 4 : 5));
    return sg == 0 ? 6 : (sg == 1 ? 5 : 7);
  };
  mbar_wait(sb + BAR_OFF + 8 * B_ONES, 0);
  uint32_t done_mask = 0;
#pragma unroll 1
  for (int sg = 0; sg < nseg; sg++) {
    const int qt = seg_qt(sg);
    int t0 = 0, t1 = 16, mode = 0;
    if (fast) {
      if (wg == 0) { if (sg == 2) { t1 = SPLIT2; mode = 2; } }
      else if (wg == 1) { if (sg == 1) { t0 = SPLIT2; mode = 1; } if (sg == 3) { t1 = SPLIT5; mode = 2; } }
      else if (sg == 1) { t0 = SPLIT5; mode = 1; }
    }
    const int row0 = qq * 512 + qt * 64;
    const uint32_t q0 = qn0, q1 = qn1, q2 = qn2, q3 = qn3;
    if (sg + 1 < nseg) {
      const uint8_t* qb = qbase + seg_qt(sg + 1) * 1024;
      qn0 = *reinterpret_cast<const uint32_t*>(qb);
      qn1 = *reinterpret_cast<const uint32_t*>(qb + 128);
      qn2 = *reinterpret_cast<const uint32_t*>(qb + PLANE);
      qn3 = *reinterpret_cast<const uint32_t*>(qb + PLANE + 128);
    }
    float O[12];
#pragma unroll
    for (int i = 0; i < 12; i++) O[i] = 0.f;
    if (fast) {
      const uint64_t dK = dK0 + DK_STEP * (uint64_t)t0, dV = dV0 + DV_STEP * (uint64_t)t0;
      if (sg == 0) {
        attn_segment<true>(O, q0, q1, q2, q3, dK, dV, t0, t1, sKV, cmask, ca2);
      } else {
        attn_segment<false>(O, q0, q1, q2, q3, dK, dV, t0, t1, sKV, cmask, ca2);
      }
    } else {
      float m0 = -INFINITY, m1 = -INFINITY;
#pragma unroll 1
      for (int j = 0; j < 32; j++) {
        float S[32];
        uint32_t P[16];
        mbar_wait(sKV + 8 * (j >> 2), 0);
        const uint64_t dK = dK0 + DK_STEP * (uint64_t)(j >> 1) + (uint64_t)((j & 1) * 64);
        const uint64_t dV = dV0 + DV_STEP * (uint64_t)(j >> 1) + (uint64_t)((j & 1) * 64);
        wg_fence();
        qk_n64(S, q0, q1, q2, q3, dK);
        wg_commit();
        wg_wait<0>();
        reg_fence(S);
        float x0 = S[0], x1 = S[2];
#pragma unroll
        for (int i = 0; i < 8; i++) {
          x0 = fmaxf(x0, fmaxf(S[4 * i], S[4 * i + 1]));
          x1 = fmaxf(x1, fmaxf(S[4 * i + 2], S[4 * i + 3]));
        }
        x0 = fmaxf(x0, __shfl_xor_sync(0xffffffffu, x0, 1)); x0 = fmaxf(x0, __shfl_xor_sync(0xffffffffu, x0, 2));
        x1 = fmaxf(x1, __shfl_xor_sync(0xffffffffu, x1, 1)); x1 = fmaxf(x1, __shfl_xor_sync(0xffffffffu, x1, 2));
        const float n0 = fmaxf(m0, x0), n1 = fmaxf(m1, x1);
        const float s0 = ex2(m0 - n0), s1 = ex2(m1 - n1);
        m0 = n0; m1 = n1;
        reg_fence(O);
#pragma unroll
        for (int i = 0; i < 3; i++) { O[4 * i] *= s0; O[4 * i + 1] *= s0; O[4 * i + 2] *= s1; O[4 * i + 3] *= s1; }
#pragma unroll
        for (int i = 0; i < 8; i++) {
          P[2 * i] = pack_bf16(ex2(S[4 * i] - n0), ex2(S[4 * i + 1] - n0));
          P[2 * i + 1] = pack_bf16(ex2(S[4 * i + 2] - n1), ex2(S[4 * i + 3] - n1));
        }
        wg_fence();
#pragma unroll
        for (int k = 0; k < 4; k++) pv_n24(O, P[4 * k], P[4 * k + 1], P[4 * k + 2], P[4 * k + 3], dV + (uint64_t)(k * 16));
        wg_commit();
        wg_wait<0>();
      }
    }
    reg_fence(O);
    float* part = reinterpret_cast<float*>(smem + P2_PART_OFF + (qt == 5 ? 5120 : 0)) + (tid & 127);
    if (mode == 1) {
#pragma unroll
      for (int i = 0; i < 8; i++) part[i * 128] = O[i];
      part[8 * 128] = O[8]; part[9 * 128] = O[10];
      if (qt == 2) named_arrive(4, 256); else named_arrive(5, 256);
      continue;
    }
    if (mode == 2) {
      if (qt == 2) named_bar(4, 256); else named_bar(5, 256);
#pragma unroll
      for (int i = 0; i < 8; i++) O[i] += part[i * 128];
      O[8] += part[8 * 128]; O[10] += part[9 * 128];
    }
    float inv0, inv1;
    asm("rcp.approx.ftz.f32 %0, %1;" : "=f"(inv0) : "f"(O[8]));
    asm("rcp.approx.ftz.f32 %0, %1;" : "=f"(inv1) : "f"(O[10]));
    const int r64 = row0 >> 6;
    done_mask |= 1u << r64;
    uint8_t* op = g_o + ((size_t)r64 * O_SLABS + head) * SLAB + warp * 512 + lane * 4;
    *reinterpret_cast<uint32_t*>(op) = pack_bf16(O[0] * inv0, O[1] * inv0);
    *reinterpret_cast<uint32_t*>(op + 128) = pack_bf16(O[4] * inv0, O[5] * inv0);
    *reinterpret_cast<uint32_t*>(op + 256) = pack_bf16(O[2] * inv1, O[3] * inv1);
    *reinterpret_cast<uint32_t*>(op + 384) = pack_bf16(O[6] * inv1, O[7] * inv1);
  }
  if (wg == 0) named_bar(1, 128); else if (wg == 1) named_bar(2, 128); else named_bar(3, 128);
  if ((tid & 127) == 0) {
    fence_gpu();
    while (done_mask) {
      const int r64 = __ffs(done_mask) - 1;
      done_mask &= done_mask - 1;
      flag_add(&g_flags.o[r64]);
    }
  }
  __syncwarp();
  named_arrive(6, 512);
}

__device__ __forceinline__ void output(uint8_t* smem, uint32_t sb, const __nv_bfloat16* __restrict__ x, const Params& P, int warp, int lane, int tid, int bid) {
  const uint32_t bars = sb + BAR_OFF, kvb = sb + P2_KV_OFF, ring = sb;
  const int r64 = bid >> 2, nb = bid & 3;
  const bool leader = (tid == 384);
  const uint8_t* hsrc = g_h + (size_t)r64 * H_SLABS * SLAB;
  constexpr int DN_ITERS = 22;
  auto load_dn = [&](int it) {
    const int s = it % DN_STAGES;
    const uint32_t dst = ring + s * DN_BYTES, bar = bars + 8 * (B_DNF + s);
    const uint32_t abytes = it == DN_ITERS - 1 ? 2 * SLAB : 4 * SLAB;
    mbar_expect_tx(bar, 16384 + abytes);
    bulk_g2s(dst + 16384, hsrc + (size_t)(4 * it) * SLAB, abytes, bar);
    tma_2d(dst, &P.wd, nb * 128, it * 64, bar);
    tma_2d(dst + 8192, &P.wd, nb * 128 + 64, it * 64, bar);
  };
  if (leader) {
    flag_wait(&g_flags.h[r64], 8);
    asm volatile("fence.proxy.async;" ::: "memory");
    mbar_wait(bars + 8 * (B_KV + 5), 0);
    for (int it = 0; it < DN_STAGES; it++) load_dn(it);
  }
  __syncwarp();
  float acc[64];
#pragma unroll
  for (int i = 0; i < 64; i++) acc[i] = 0.f;
  reg_fence(acc);
#pragma unroll 1
  for (int it = 0; it < DN_ITERS - 1; it++) {
    const int s = it % DN_STAGES;
    mbar_wait(bars + 8 * (B_DNF + s), (it / DN_STAGES) & 1);
    const uint32_t st = ring + s * DN_BYTES;
    const uint64_t dA = mkdesc(st + 16384, 128, 256, 0), dB = mkdesc(st, 8192, 1024, 1);
    wg_fence();
#pragma unroll
    for (int kk = 0; kk < 4; kk++) mma_n128_t(acc, dA + kk * 128, dB + kk * 128, 1);
    wg_commit();
    wg_wait<0>();
    if (lane == 0) mbar_arrive(bars + 8 * (B_DNE + s));
    if (leader && it + DN_STAGES < DN_ITERS) {
      mbar_wait(bars + 8 * (B_DNE + s), (it / DN_STAGES) & 1);
      load_dn(it + DN_STAGES);
    }
    __syncwarp();
  }
  {
    constexpr int it = DN_ITERS - 1, s = it % DN_STAGES;
    mbar_wait(bars + 8 * (B_DNF + s), (it / DN_STAGES) & 1);
    const uint32_t st = ring + s * DN_BYTES;
    const uint64_t dA = mkdesc(st + 16384, 128, 256, 0), dB = mkdesc(st, 8192, 1024, 1);
    wg_fence();
    mma_n128_t(acc, dA, dB, 1);
    mma_n128_t(acc, dA + 128, dB + 128, 1);
    wg_commit();
  }
  wg_wait<0>();
  reg_fence(acc);
  {
    const int row = r64 * 64 + warp * 16 + (lane >> 2);
    const float rr0 = __ldcg(g_rr + row), rr1 = __ldcg(g_rr + row + 8);
#pragma unroll
    for (int j = 0; j < 16; j++) { acc[4 * j] *= rr0; acc[4 * j + 1] *= rr0; acc[4 * j + 2] *= rr1; acc[4 * j + 3] *= rr1; }
  }
  named_bar(7, 128);
  if (leader) {
    for (int c = 0; c < 8; c++) mbar_expect_tx(bars + 8 * (B_WO + c), 16384 + 8192);
    for (int c = 0; c < 5; c++) {
      tma_2d(ring + c * 16384, &P.wo, nb * 128, c * 64, bars + 8 * (B_WO + c));
      tma_2d(ring + c * 16384 + 8192, &P.wo, nb * 128 + 64, c * 64, bars + 8 * (B_WO + c));
    }
  }
  const int g = lane >> 2, c4 = lane & 3;
  uint32_t xr[32];
  {
    const __nv_bfloat16* xp = x + (size_t)(r64 * 64 + warp * 16 + g) * DM + nb * 128 + 2 * c4;
#pragma unroll
    for (int j = 0; j < 16; j++) {
      xr[2 * j] = __ldg(reinterpret_cast<const uint32_t*>(xp + 8 * j));
      xr[2 * j + 1] = __ldg(reinterpret_cast<const uint32_t*>(xp + 8 * DM + 8 * j));
    }
  }
  unsigned int ticket = 0;
  named_bar(6, 512);
  if (leader) {
    for (int c = 5; c < 8; c++) {
      tma_2d(kvb + (c - 5) * 16384, &P.wo, nb * 128, c * 64, bars + 8 * (B_WO + c));
      tma_2d(kvb + (c - 5) * 16384 + 8192, &P.wo, nb * 128 + 64, c * 64, bars + 8 * (B_WO + c));
    }
  }
  if (tid == 416) {
    flag_wait(&g_flags.o[r64], 32);
    asm volatile("fence.proxy.async;" ::: "memory");
    const uint8_t* osrc = g_o + (size_t)r64 * O_SLABS * SLAB;
    for (int c = 0; c < 8; c++) bulk_g2s(kvb + 49152 + c * 8192, osrc + (size_t)c * 8192, 8192, bars + 8 * (B_WO + c));
    asm volatile("atom.acq_rel.gpu.global.add.u32 %0, [%1], 1;" : "=r"(ticket) : "l"(&g_flags.done) : "memory");
  }
  __syncwarp();
#pragma unroll 1
  for (int c = 0; c < 8; c++) {
    mbar_spin(bars + 8 * (B_WO + c), 0);
    const uint32_t bs = c < 5 ? ring + c * 16384 : kvb + (c - 5) * 16384;
    const uint64_t dA = mkdesc(kvb + 49152 + c * 8192, 128, 256, 0), dB = mkdesc(bs, 8192, 1024, 1);
    wg_fence();
#pragma unroll
    for (int kk = 0; kk < 4; kk++) mma_n128_t(acc, dA + kk * 128, dB + kk * 128, 1);
    wg_commit();
  }
  wg_wait<0>();
  reg_fence(acc);
  const uint32_t stg = kvb + 114688;
  const int m = lane >> 3, r = warp * 16 + (m & 1) * 8 + (lane & 7);
#pragma unroll
  for (int jj = 0; jj < 8; jj++) {
    uint32_t o[4];
#pragma unroll
    for (int e = 0; e < 2; e++) {
      const int j = 2 * jj + e;
      o[2 * e] = pack_bf16(acc[4 * j] + bf_lo(xr[2 * j]), acc[4 * j + 1] + bf_hi(xr[2 * j]));
      o[2 * e + 1] = pack_bf16(acc[4 * j + 2] + bf_lo(xr[2 * j + 1]), acc[4 * j + 3] + bf_hi(xr[2 * j + 1]));
    }
    const int j = 2 * jj + (m >> 1);
    const uint32_t addr = stg + (j >> 3) * 8192 + r * 128 + (((j & 7) ^ (r & 7)) << 4);
    asm volatile("stmatrix.sync.aligned.m8n8.x4.shared.b16 [%0], {%1, %2, %3, %4};" ::"r"(addr), "r"(o[0]), "r"(o[1]), "r"(o[2]), "r"(o[3]) : "memory");
  }
  fence_async_smem();
  named_bar(7, 128);
  if (tid == 416 && ticket == 127u) {
    g_flags.qkv = 0u;
    for (int i = 0; i < 32; i++) { g_flags.h[i] = 0u; g_flags.o[i] = 0u; }
    for (int i = 0; i < 16; i++) g_flags.cs[i] = 0u;
    g_flags.done = 0u;
  }
  if (leader) {
    asm volatile("cp.async.bulk.tensor.2d.global.shared::cta.bulk_group [%0, {%2, %3}], [%1];" ::"l"(&P.out), "r"(stg), "r"(nb * 128), "r"(r64 * 64) : "memory");
    asm volatile("cp.async.bulk.tensor.2d.global.shared::cta.bulk_group [%0, {%2, %3}], [%1];" ::"l"(&P.out), "r"(stg + 8192), "r"(nb * 128 + 64), "r"(r64 * 64) : "memory");
    asm volatile("cp.async.bulk.commit_group;" ::: "memory");
    asm volatile("cp.async.bulk.wait_group.read 0;" ::: "memory");
  }
}

__global__ void __launch_bounds__(512, 1)
fused_kernel(const __nv_bfloat16* __restrict__ x, const __grid_constant__ Params P) {
  extern __shared__ __align__(1024) uint8_t smem[];
  const uint32_t sb = smem_u32(smem), bars = sb + BAR_OFF;
  const int tid = threadIdx.x, lane = tid & 31;
  const int wg = __shfl_sync(0xffffffffu, tid >> 7, 0), warp8 = __shfl_sync(0xffffffffu, tid >> 5, 0);
  const int warp = warp8 & 3;
  const int bid = __shfl_sync(0xffffffffu, (int)blockIdx.x, 0);
  const int rb = bid >> 3, cg = bid & 7;
  if (tid == 256) {
    tma_prefetch_desc(&P.wqkv); tma_prefetch_desc(&P.x);
    mbar_init(bars + 8 * B_FULL, 1); mbar_init(bars + 8 * B_X, 1);
    fence_mbar_init();
    phase1_first_loads(sb, P, bid >> 3, bid & 7);
  }
  if (tid == 0) {
    for (int s = 0; s < P1_STAGES; s++) { if (s) mbar_init(bars + 8 * (B_FULL + s), 1); mbar_init(bars + 8 * (B_EMPTY + s), 8); }
    for (int w = 1; w < 8; w++) mbar_init(bars + 8 * (B_X + w), 1);
    for (int c = 0; c < 9; c++) mbar_init(bars + 8 * (B_KV + c), 1);
    for (int s = 0; s < DN_STAGES; s++) { mbar_init(bars + 8 * (B_DNF + s), 1); mbar_init(bars + 8 * (B_DNE + s), 4); }
    for (int c = 0; c < 8; c++) mbar_init(bars + 8 * (B_WO + c), 1);
    mbar_init(bars + 8 * B_CS, 4); mbar_init(bars + 8 * (B_CS + 1), 4); mbar_init(bars + 8 * B_ONES, 4); mbar_init(bars + 8 * B_S8, 1); mbar_init(bars + 8 * B_SL, 1);
    mbar_arrive(bars + 8 * (B_KV + 8));
    fence_mbar_init();
  }
  __syncthreads();

  AttnPre pre = {};
  if (wg < 2) {
    asm volatile("setmaxnreg.inc.sync.aligned.u32 216;");
    phase1_mma(smem, sb, wg, warp8, lane, tid, bid, pre);
  } else {
    if (wg == 2) {
      asm volatile("setmaxnreg.dec.sync.aligned.u32 32;");
      if (tid == 256) phase1_producer(sb, P, rb, cg);
      __syncwarp();
      named_bar(9, 416);
      if (tid == 256) {
        asm volatile("fence.proxy.async;" ::: "memory");
        const uint8_t* img = g_att + KV_OFF + (size_t)(bid >> 2) * KV_BYTES;
        const uint32_t kvb = sb + P2_KV_OFF;
        for (int c = 0; c < 8; c++) {
          const uint32_t bar = bars + 8 * (B_KV + c);
          mbar_expect_tx(bar, 16384);
          bulk_g2s(kvb + c * 8192, img + c * 8192, 8192, bar);
          bulk_g2s(kvb + 98304 + c * 4096, img + 98304 + c * 4096, 4096, bar);
          bulk_g2s(kvb + 65536 + c * 4096, img + 65536 + c * 4096, 4096, bar);
        }
      }
      __syncwarp();
      pre = attn_prefetch(2, warp, lane, bid);
    } else {
      asm volatile("setmaxnreg.dec.sync.aligned.u32 48;");
      float* csp = g_csp + (size_t)cg * 16 * CS_N;
      mbar_wait(bars + 8 * B_SL, 0);
      colsum_slice(smem + 7 * 16384, 4096, 96, csp + rb * CS_N, tid & 127);
      if (lane == 0) mbar_arrive(bars + 8 * B_CS);
      named_bar(7, 128);
      if (tid == 384) { fence_gpu(); flag_add(&g_flags.cs[cg]); flag_wait(&g_flags.cs[cg], 16); }
      named_bar(7, 128);
      colsum_gather(smem, csp, 0, 192, tid & 127);
      named_arrive(12, 384);
      mbar_wait(bars + 8 * B_S8, 0);
      colsum_slice(smem + P1_RING_OFF, 4096, 88, csp + rb * CS_N + 192, tid & 127);
      colsum_slice(smem + P1_RING_OFF + 12288, 4096, 88, csp + rb * CS_N + 368, tid & 127);
      if (lane == 0) mbar_arrive(bars + 8 * (B_CS + 1));
      named_bar(7, 128);
      if (tid == 384) { fence_gpu(); flag_add(&g_flags.cs[8 + cg]); }
      if (warp == 1 || warp == 2) {
        if (warp == 1) named_bar(10, 160); else named_bar(11, 160);
        if (lane == 0) { fence_gpu(); flag_add(&g_flags.qkv); }
        __syncwarp();
      }
      if (tid == 384) flag_wait(&g_flags.cs[8 + cg], 16);
      named_bar(7, 128);
      colsum_gather(smem, csp, 192, 352, tid & 127);
      named_arrive(13, 384);
      if (warp == 3) {
        if (lane == 0) flag_wait(&g_flags.qkv, 256);
        __syncwarp();
        named_arrive(9, 416);
      }
      if (tid == 384) { tma_prefetch_desc(&P.wd); tma_prefetch_desc(&P.wo); tma_prefetch_desc(&P.out); }
      named_bar(8, 384);
      reinterpret_cast<uint4*>(smem + ONES_OFF)[tid & 127] = make_uint4(0x3f803f80u, 0x3f803f80u, 0x3f803f80u, 0x3f803f80u);
      fence_async_smem();
      __syncwarp();
      if (lane == 0) mbar_arrive(bars + 8 * B_ONES);
      if (tid == 384) {
        const uint32_t bytes = (cg < 7 ? 11 : 9) * SLAB;
#pragma unroll
        for (int w = 0; w < 2; w++)
          asm volatile("cp.async.bulk.global.shared::cta.bulk_group [%0], [%1], %2;" ::"l"(g_h + ((size_t)(rb * 2 + w) * H_SLABS + cg * 11) * SLAB), "r"(sb + w * 11 * SLAB), "r"(bytes) : "memory");
        asm volatile("cp.async.bulk.commit_group;" ::: "memory");
        asm volatile("cp.async.bulk.wait_group 0;" ::: "memory");
        asm volatile("fence.proxy.async;" ::: "memory");
        fence_gpu();
        flag_add(&g_flags.h[rb * 2]);
        flag_add(&g_flags.h[rb * 2 + 1]);
      }
      __syncwarp();
    }
    asm volatile("setmaxnreg.inc.sync.aligned.u32 128;");
  }
  if (wg < 3) attention(smem, sb, wg, warp, lane, tid, bid, pre);
  else output(smem, sb, x, P, warp, lane, tid, bid);
}

typedef CUresult (*EncodeFn)(CUtensorMap*, CUtensorMapDataType, cuuint32_t, void*, const cuuint64_t*, const cuuint64_t*,
                             const cuuint32_t*, const cuuint32_t*, CUtensorMapInterleave, CUtensorMapSwizzle,
                             CUtensorMapL2promotion, CUtensorMapFloatOOBfill);

void make_map(EncodeFn fn, CUtensorMap* tm, const void* ptr, uint64_t inner, uint64_t outer, uint32_t box_inner, uint32_t box_outer) {
  cuuint64_t dims[2] = {inner, outer};
  cuuint64_t strides[1] = {inner * 2};
  cuuint32_t box[2] = {box_inner, box_outer};
  cuuint32_t estr[2] = {1, 1};
  fn(tm, CU_TENSOR_MAP_DATA_TYPE_BFLOAT16, 2, const_cast<void*>(ptr), dims, strides, box, estr, CU_TENSOR_MAP_INTERLEAVE_NONE,
     CU_TENSOR_MAP_SWIZZLE_128B, CU_TENSOR_MAP_L2_PROMOTION_NONE, CU_TENSOR_MAP_FLOAT_OOB_FILL_NONE);
}

struct HostState {
  bool ready;
  const void* key[8];
  Params p;
};
HostState g_host;

}

extern "C" void kernel_launch(void* const* d_in, const int* in_sizes, int n_in, void* d_out, int out_size) {
  (void)in_sizes; (void)n_in; (void)out_size;
  bool same = g_host.ready;
  for (int i = 0; i < 7 && same; i++) same = g_host.key[i] == d_in[i];
  same = same && g_host.key[7] == d_out;
  if (!same) {
    void* fnp = nullptr;
    cudaDriverEntryPointQueryResult qr;
    cudaGetDriverEntryPoint("cuTensorMapEncodeTiled", &fnp, cudaEnableDefault, &qr);
    EncodeFn fn = (EncodeFn)fnp;
    make_map(fn, &g_host.p.x, d_in[0], DM, SEQ, 64, 128);
    make_map(fn, &g_host.p.out, d_out, DM, SEQ, 64, 64);
    make_map(fn, &g_host.p.wqkv, d_in[1], 3 * DM, DM, 64, 64);
    make_map(fn, &g_host.p.wqkv32, d_in[1], 3 * DM, DM, 64, 32);
    make_map(fn, &g_host.p.wg, d_in[4], FF, DM, 64, 32);
    make_map(fn, &g_host.p.wu, d_in[5], FF, DM, 64, 32);
    make_map(fn, &g_host.p.wo, d_in[2], DM, DM, 64, 64);
    make_map(fn, &g_host.p.wd, d_in[6], DM, FF, 64, 64);
    cudaFuncSetAttribute(fused_kernel, cudaFuncAttributeMaxDynamicSharedMemorySize, SMEM_BYTES);
    for (int i = 0; i < 7; i++) g_host.key[i] = d_in[i];
    g_host.key[7] = d_out;
    g_host.ready = true;
  }
  fused_kernel<<<128, 512, SMEM_BYTES, cudaStreamPerThread>>>((const __nv_bfloat16*)d_in[0], g_host.p);
}
```
